```python
import torch

def _softmax(x, axis=-1):
    return torch.softmax(x, dim=axis)
def _gelu(x):
    return torch.nn.functional.gelu(x, approximate="tanh")
def _silu(x):
    return torch.nn.functional.silu(x)
def _sigmoid(x):
    return torch.sigmoid(x)
def _layernorm(x, axis=-1, eps=1e-5):
    m = x.mean(dim=axis, keepdim=True)
    v = x.var(dim=axis, keepdim=True, unbiased=False)
    return (x - m) / torch.sqrt(v + eps)
def _scatter_add(tgt, idx, src, axis=0):
    return tgt.clone().index_add_(axis, idx, src)
def _segment_sum(src, seg, n):
    out = torch.zeros((n,) + src.shape[1:], dtype=src.dtype)
    return out.index_add_(0, seg, src)
def _pad(x, pw):
    flat = tuple(v for pair in reversed(pw) for v in pair)
    return torch.nn.functional.pad(x, flat)

kernel_name = 'standalone__gqa_block_cached__decode'

def setup_inputs():

    _w = (lambda a: (lambda t: t.to(torch.bfloat16) if t.is_floating_point() else t)(torch.as_tensor(a)))
    B, Sq, D = 1, 1, 576
    Hq, Hkv, Sk, Dh = 32, 16, 65536, 128
    assert Hq % Hkv == 0, (Hq, Hkv)
    return {
        "x": _w((lambda *s: torch.randn(*s, dtype=torch.bfloat16) * 0.8)(B, Sq, D)),
        "k_cache": _w((lambda *s: torch.randn(*s, dtype=torch.bfloat16) * 0.8)(B, Hkv, Sk, Dh)),
        "v_cache": _w((lambda *s: torch.randn(*s, dtype=torch.bfloat16) * 0.05)(B, Hkv, Sk, Dh)),
        "wq": _w((lambda *s: torch.randn(*s, dtype=torch.bfloat16) * 0.8)(D, Hq * Dh) * (D ** -0.5)),
        "wo": _w((lambda *s: torch.randn(*s, dtype=torch.bfloat16) * 0.05)(Hq * Dh, D) * ((Hq * Dh) ** -0.5)),
    }

def reference(x, k_cache, v_cache, wq, wo):
    B, Sq, D = x.shape
    Hq, Dh = 32, 128
    Hkv = k_cache.shape[1]
    rep = Hq // Hkv
    q = (lambda x, *d: x.permute(*d))((x @ wq).reshape(B, Sq, Hq, Dh), 0, 2, 1, 3)
    k = (lambda x, n, axis: torch.repeat_interleave(x, n, dim=axis))(k_cache, rep, axis=1)
    v = (lambda x, n, axis: torch.repeat_interleave(x, n, dim=axis))(v_cache, rep, axis=1)
    scores = torch.einsum("bhqd,bhkd->bhqk", q, k) * (Dh ** -0.5)
    p = _softmax(scores, axis=-1)
    o = torch.einsum("bhqk,bhkd->bhqd", p, v)
    return (lambda x, *d: x.permute(*d))(o, 0, 2, 1, 3).reshape(B, Sq, Hq * Dh) @ wo
```

```cpp
#include <cuda_runtime.h>
#include <cuda_bf16.h>
#include <stdint.h>

#define WQPF ".L2::256B"
namespace gqa {

constexpr int kD = 576;
constexpr int kHkv = 16;
constexpr int kSk = 65536;
constexpr int kDh = 128;
constexpr int kQ = 4096;
constexpr int kG = 128;
constexpr int kTP = 32;
constexpr int kTileBytes = kTP * kDh * 2;
constexpr int kStageBytes = 2 * kTileBytes;
constexpr int kNTiles = kHkv * kSk / kTP;
constexpr int kHeadShift = 11;
#define GQA_S 10
#define GQA_W 3
#define GQA_W0 2
#define GQA_TD 2
#define GQA_STARTDELAY 600
#define GQA_WOAT -1
#define GQA_WOPER 6
#define GQA_WOSTEPS 3
#define JOBDELAY 9000
#define QPOLLNS 100
#define POLLNS 0
constexpr int kS = GQA_S;
constexpr int kW = GQA_W;
constexpr int kW0 = GQA_W0;
constexpr int kTD = GQA_TD;
constexpr int kWoPer = GQA_WOPER, kWoSteps = GQA_WOSTEPS;
static_assert(kW < kS && kW0 <= kW, "window");
constexpr int kThreads = 288;
constexpr int kWoRowBytes = kD * 2;
constexpr int kHS = 132;
constexpr int kCS = 288;
constexpr int kWS = 2 * kCS;
constexpr int kNRed = 96;

constexpr int kOffRing = 0;
constexpr int kOffWo = kOffRing + kS * kStageBytes;
constexpr int kOffQ = kOffWo + 32 * kWoRowBytes;
constexpr int kOffStg = kOffQ + kQ * 2;
constexpr int kOffMl = kOffStg + 4 * kWS * 4;
constexpr int kOffRed = kOffMl + 64;
constexpr int kOffCmb = kOffRed + 1024;
constexpr int kOffO = kOffCmb + 16 * 4 * 16;
constexpr int kOffTile = kOffO + 128;
constexpr int kOffBar = kOffTile + 64;
constexpr int kNumBars = 2 * kS + 2 + 3;
constexpr int kSmemBytes = kOffBar + kNumBars * 8;
static_assert(kSmemBytes <= 232448, "smem");
static_assert(kS <= 16, "tile id array");

struct __align__(128) Scratch {
  unsigned int ticket;
  unsigned int epoch;
  unsigned int pad[30];
  uint2 qpk[kQ / 2];
  uint4 box[kG][3][kG];
};
__device__ Scratch g_scr;

#define DBG(i)
#define DBG2(k, i)

constexpr long long kSpinLimit = 4000000000LL;
constexpr int kPollLimit = 1 << 22;

__device__ __forceinline__ void mbar_init(uint32_t bar, int cnt) {
  asm volatile("mbarrier.init.shared.b64 [%0], %1;" ::"r"(bar), "r"(cnt) : "memory");
}
__device__ __forceinline__ void mbar_expect_tx(uint32_t bar, uint32_t bytes) {
  asm volatile("mbarrier.arrive.expect_tx.shared.b64 _, [%0], %1;" ::"r"(bar), "r"(bytes) : "memory");
}
__device__ __forceinline__ void mbar_arrive(uint32_t bar) {
  asm volatile("mbarrier.arrive.shared.b64 _, [%0];" ::"r"(bar) : "memory");
}
__device__ __forceinline__ bool mbar_try(uint32_t bar, uint32_t parity) {
  uint32_t ok;
  asm volatile(
      "{\n.reg .pred p;\n"
      "mbarrier.try_wait.parity.shared.b64 p, [%1], %2;\n"
      "selp.u32 %0, 1, 0, p;\n}"
      : "=r"(ok)
      : "r"(bar), "r"(parity)
      : "memory");
  return ok != 0;
}
__device__ __noinline__ void mbar_wait_slow(uint32_t bar, uint32_t parity) {
  long long t0 = clock64();
  while (!mbar_try(bar, parity)) {
    if (clock64() - t0 > kSpinLimit) __trap();
  }
}
__device__ __forceinline__ void mbar_wait(uint32_t bar, uint32_t parity) {
  if (mbar_try(bar, parity)) return;
  if (mbar_try(bar, parity)) return;
  mbar_wait_slow(bar, parity);
}
__device__ __forceinline__ void bulk_load(uint32_t dst, const void* src, uint32_t bytes, uint32_t bar,
                                          uint64_t pol) {
  asm volatile(
      "cp.async.bulk.shared::cluster.global.mbarrier::complete_tx::bytes.L2::cache_hint [%0], [%1], %2, [%3], %4;"
      ::"r"(dst), "l"(src), "r"(bytes), "r"(bar), "l"(pol)
      : "memory");
}
__device__ __forceinline__ uint4 lds128(uint32_t a) {
  uint4 v;
  asm volatile("ld.shared.v4.u32 {%0,%1,%2,%3}, [%4];" : "=r"(v.x), "=r"(v.y), "=r"(v.z), "=r"(v.w) : "r"(a) : "memory");
  return v;
}
__device__ __forceinline__ void mma16816(float (&c)[4], uint32_t a0, uint32_t a1, uint32_t a2, uint32_t a3,
                                         uint32_t b0, uint32_t b1) {
  asm volatile(
      "mma.sync.aligned.m16n8k16.row.col.f32.bf16.bf16.f32 {%0,%1,%2,%3}, {%4,%5,%6,%7}, {%8,%9}, {%0,%1,%2,%3};"
      : "+f"(c[0]), "+f"(c[1]), "+f"(c[2]), "+f"(c[3])
      : "r"(a0), "r"(a1), "r"(a2), "r"(a3), "r"(b0), "r"(b1));
}
__device__ __forceinline__ float ex2(float x) {
  float y;
  asm("ex2.approx.ftz.f32 %0, %1;" : "=f"(y) : "f"(x));
  return y;
}
__device__ __forceinline__ float lg2(float x) {
  float y;
  asm("lg2.approx.f32 %0, %1;" : "=f"(y) : "f"(x));
  return y;
}
__device__ __forceinline__ float rcp(float x) {
  float y;
  asm("rcp.approx.f32 %0, %1;" : "=f"(y) : "f"(x));
  return y;
}
__device__ __forceinline__ float warp_max(float v) {
  int k = __float_as_int(v);
  k ^= (k >> 31) & 0x7fffffff;
  k = __reduce_max_sync(0xffffffffu, k);
  k ^= (k >> 31) & 0x7fffffff;
  return __int_as_float(k);
}
__device__ __forceinline__ bool mbar_test(uint32_t bar, uint32_t parity) {
  uint32_t ok;
  asm volatile(
      "{\n.reg .pred p;\n"
      "mbarrier.test_wait.parity.shared.b64 p, [%1], %2;\n"
      "selp.u32 %0, 1, 0, p;\n}"
      : "=r"(ok)
      : "r"(bar), "r"(parity)
      : "memory");
  return ok != 0;
}
__device__ __forceinline__ void st_pkt(uint4* p, uint32_t x, uint32_t y, uint32_t z, uint32_t w) {
  asm volatile(
      "{\n.reg .b128 v;\nmov.b128 v, {%1, %2};\nst.relaxed.gpu.global.b128 [%0], v;\n}"
      ::"l"(p), "l"((uint64_t)x | ((uint64_t)y << 32)), "l"((uint64_t)z | ((uint64_t)w << 32))
      : "memory");
}
__device__ __forceinline__ uint4 ld_pkt(const uint4* p) {
  uint64_t lo, hi;
  asm volatile(
      "{\n.reg .b128 v;\nld.relaxed.gpu.global.b128 v, [%2];\nmov.b128 {%0, %1}, v;\n}"
      : "=l"(lo), "=l"(hi)
      : "l"(p)
      : "memory");
  return make_uint4((uint32_t)lo, (uint32_t)(lo >> 32), (uint32_t)hi, (uint32_t)(hi >> 32));
}
__device__ __forceinline__ void bar_sync(int id, int n) { asm volatile("bar.sync %0, %1;" ::"r"(id), "r"(n) : "memory"); }
__device__ __forceinline__ void bar_arrive(int id, int n) { asm volatile("bar.arrive %0, %1;" ::"r"(id), "r"(n) : "memory"); }
__device__ __forceinline__ float bf_lo(uint32_t v) { return __uint_as_float(v << 16); }
__device__ __forceinline__ float bf_hi(uint32_t v) { return __uint_as_float(v & 0xffff0000u); }
__device__ __forceinline__ uint32_t pack_bf16(float lo, float hi) {
  uint32_t r;
  asm("cvt.rn.bf16x2.f32 %0, %1, %2;" : "=r"(r) : "f"(hi), "f"(lo));
  return r;
}
__device__ __forceinline__ float round_bf16(float v) { return bf_lo(pack_bf16(v, 0.f)); }

__device__ __forceinline__ float2 finish_o(const float4* rec) {
  float4 r0 = rec[0], r1 = rec[1], r2 = rec[2], r3 = rec[3];
  float M = fmaxf(fmaxf(r0.x, r1.x), fmaxf(r2.x, r3.x));
  float f0 = ex2(r0.x - M), f1 = ex2(r1.x - M), f2 = ex2(r2.x - M), f3 = ex2(r3.x - M);
  float a = f0 * r0.y + f1 * r1.y + f2 * r2.y + f3 * r3.y;
  float b = f0 * r0.z + f1 * r1.z + f2 * r2.z + f3 * r3.z;
  float s = f0 * r0.w + f1 * r1.w + f2 * r2.w + f3 * r3.w;
  const float inv = rcp(s);
  return make_float2(round_bf16(a * inv), round_bf16(b * inv));
}

constexpr float kNegBig = -3.0e38f;

__global__ void __launch_bounds__(kThreads, 1)
gqa_decode_kernel(const __nv_bfloat16* __restrict__ x, const __nv_bfloat16* __restrict__ kc,
                  const __nv_bfloat16* __restrict__ vc, const __nv_bfloat16* __restrict__ wq,
                  const __nv_bfloat16* __restrict__ wo, __nv_bfloat16* __restrict__ out) {
  extern __shared__ __align__(128) unsigned char smem[];
  const uint32_t sb = (uint32_t)__cvta_generic_to_shared(smem);
  const int tid = threadIdx.x, warp = tid >> 5, lane = tid & 31;
  const int cta = blockIdx.x;

  const uint32_t bar_full = sb + kOffBar;
  const uint32_t bar_empty = bar_full + 8 * kS;
  const uint32_t bar_q = bar_empty + 8 * kS;
  const uint32_t bar_stg_full = bar_q + 16;
  const uint32_t bar_stg_empty = bar_stg_full + 8;
  const uint32_t bar_wo = bar_stg_empty + 8;
  volatile int* tile_s = reinterpret_cast<volatile int*>(smem + kOffTile);

  if (warp == 8) {
    uint64_t pol;
    asm volatile("createpolicy.fractional.L2::evict_first.b64 %0, 1.0;" : "=l"(pol));
    unsigned int tk[kTD];
    const char* kb = reinterpret_cast<const char*>(kc);
    const char* vb = reinterpret_cast<const char*>(vc);
    auto issue = [&](int slot, int tile) {
      tile_s[slot] = tile;
      const uint32_t fb = bar_full + 8 * slot;
      const uint32_t dst = sb + kOffRing + slot * kStageBytes;
      mbar_expect_tx(fb, kStageBytes);
      bulk_load(dst, kb + (size_t)tile * kTileBytes, kTileBytes, fb, pol);
      bulk_load(dst + kTileBytes, vb + (size_t)tile * kTileBytes, kTileBytes, fb, pol);
    };
    const long long t_start = clock64();
    if (lane == 0) {
      DBG(0);
#pragma unroll
      for (int i = 0; i < kTD; i++) tk[i] = atomicAdd(&g_scr.ticket, 1u);
      for (int i = 0; i < kS; i++) {
        mbar_init(bar_full + 8 * i, 1);
        mbar_init(bar_empty + 8 * i, 4);
      }
      mbar_init(bar_q, 2);
      mbar_init(bar_q + 8, 4);
      mbar_init(bar_stg_full, 4);
      mbar_init(bar_stg_empty, 4);
      mbar_init(bar_wo, 1);
      asm volatile("fence.mbarrier_init.release.cluster;" ::: "memory");
      asm volatile("fence.proxy.async.shared::cta;" ::: "memory");
    }
    __syncwarp();
    bar_arrive(0, kThreads);
    if (lane == 0) {
      const char* wob = reinterpret_cast<const char*>(wo) + (size_t)(2 * cta) * kWoRowBytes;
      while (clock64() - t_start < GQA_STARTDELAY) {}
#pragma unroll
      for (int i = 0; i < kW0; i++) issue(i, cta + i * kG);
      int n_slot = kW0, w_slot = 0, inflight = kW0, win = kW0;
      uint32_t n_par = 0, w_par = 0;
      int n_issued = 0;
      auto land = [&]() {
        mbar_wait(bar_full + 8 * w_slot, w_par);
        if (++w_slot == kS) { w_slot = 0; w_par ^= 1; }
        inflight--;
      };
      while (true) {
#pragma unroll
        for (int i = 0; i < kTD; i++) {
          const int tile = (int)tk[i] + kW0 * kG;
          if (tile >= kNTiles) goto drained;
          if (win < kW && mbar_test(bar_q, 0)) win = kW;
          if (inflight >= win) land();
          mbar_wait(bar_empty + 8 * n_slot, n_par ^ 1);
          issue(n_slot, tile);
          tk[i] = atomicAdd(&g_scr.ticket, 1u);
          inflight++;
          if (++n_slot == kS) { n_slot = 0; n_par ^= 1; }
        }
        if (GQA_WOAT >= 0) {
          n_issued++;
          if (n_issued == GQA_WOAT) mbar_expect_tx(bar_wo, 32 * kWoRowBytes);
          if (n_issued >= GQA_WOAT && n_issued < GQA_WOAT + kHkv) {
            const int h = n_issued - GQA_WOAT;
            bulk_load(sb + kOffWo + h * 2 * kWoRowBytes, wob + (size_t)h * 256 * kWoRowBytes, 2 * kWoRowBytes, bar_wo, pol);
          }
        }
      }
    drained:
      DBG(1);
      unsigned int tor = 0;
#pragma unroll
      for (int i = 0; i < kTD; i++) tor |= tk[i];
      if (tor == 0xffffffffu) __trap();
      mbar_wait(bar_empty + 8 * n_slot, n_par ^ 1);
      tile_s[n_slot] = kNTiles;
      mbar_arrive(bar_full + 8 * n_slot);
      if (GQA_WOAT < 0) {
        mbar_expect_tx(bar_wo, 32 * kWoRowBytes);
#pragma unroll 1
        for (int h = 0; h < kHkv; h++) {
          if (h % kWoPer == 0 && h / kWoPer < kWoSteps && inflight > 0) land();
          bulk_load(sb + kOffWo + h * 2 * kWoRowBytes, wob + (size_t)h * 256 * kWoRowBytes, 2 * kWoRowBytes, bar_wo, pol);
        }
      }
    }
    return;
  }

  unsigned int epoch;
  {
    const int r = tid >> 2, cq = tid & 3;
    const char* wp = reinterpret_cast<const char*>(wq) + (size_t)r * (kQ * 2) + cta * 64 + cq * 16;
    uint4 w[9];
    unsigned short xv[9];
    if (tid >= 128 && tid < 144)
      asm volatile("st.relaxed.gpu.global.u64 [%0], %1;" ::"l"(&g_scr.qpk[cta * 16 + tid - 128]), "l"(0ull) : "memory");
#pragma unroll
    for (int k = 0; k < 9; k++) {
      asm volatile("ld.global.nc.L1::no_allocate" WQPF ".v4.u32 {%0,%1,%2,%3}, [%4];"
                   : "=r"(w[k].x), "=r"(w[k].y), "=r"(w[k].z), "=r"(w[k].w)
                   : "l"(wp + (size_t)k * 64 * (kQ * 2)));
    }
#pragma unroll
    for (int k = 0; k < 9; k++) {
      asm volatile("ld.global.nc.u16 %0, [%1];" : "=h"(xv[k]) : "l"(x + r + 64 * k));
    }
    asm volatile("ld.relaxed.gpu.global.u32 %0, [%1];" : "=r"(epoch) : "l"(&g_scr.epoch) : "memory");
    float a[8];
#pragma unroll
    for (int i = 0; i < 8; i++) a[i] = 0.f;
#pragma unroll
    for (int k = 0; k < 9; k++) {
      const float xf = __uint_as_float((uint32_t)xv[k] << 16);
      a[0] = fmaf(xf, bf_lo(w[k].x), a[0]);
      a[1] = fmaf(xf, bf_hi(w[k].x), a[1]);
      a[2] = fmaf(xf, bf_lo(w[k].y), a[2]);
      a[3] = fmaf(xf, bf_hi(w[k].y), a[3]);
      a[4] = fmaf(xf, bf_lo(w[k].z), a[4]);
      a[5] = fmaf(xf, bf_hi(w[k].z), a[5]);
      a[6] = fmaf(xf, bf_lo(w[k].w), a[6]);
      a[7] = fmaf(xf, bf_hi(w[k].w), a[7]);
    }
#pragma unroll
    for (int o = 4; o < 32; o <<= 1) {
#pragma unroll
      for (int i = 0; i < 8; i++) a[i] += __shfl_xor_sync(0xffffffffu, a[i], o);
    }
    float* red = reinterpret_cast<float*>(smem + kOffRed);
    if (lane < 4) {
      *reinterpret_cast<float4*>(red + warp * 32 + lane * 8) = make_float4(a[0], a[1], a[2], a[3]);
      *reinterpret_cast<float4*>(red + warp * 32 + lane * 8 + 4) = make_float4(a[4], a[5], a[6], a[7]);
    }
    bar_sync(0, kThreads);
  }
  const uint32_t tagbase = (epoch + 1u) * 32u;
  const int g = lane >> 2, t = lane & 3;

  if (warp < 4) {
    const float c = 0.08838834764831845f * 1.4426950408889634f;
    const int cls = t >> 1;
    uint32_t sel0, sel1;
    if ((g >> 2) != cls) { sel0 = 0x4444; sel1 = 0x4444; }
    else if (g & 1) { sel0 = 0x1044; sel1 = 0x3244; }
    else { sel0 = 0x4410; sel1 = 0x4432; }
    const uint32_t k_off = (warp * 8 + g) * 256 + t * 16;
    const uint32_t k_x = (g & 1) * 64;
    const uint32_t v_off = kTileBytes + (warp * 8 + 2 * t) * 256 + (g ^ (cls << 1)) * 16;
    const uint32_t q_off = sb + kOffQ + ((g >> 1) & 1) * 256 + t * 16;
    const int a_src = (t & 1) * 8;

    uint4 qf[4];
    float acc[4][4];
    float mref = kNegBig, l = 0.f;
#pragma unroll
    for (int i = 0; i < 4; i++)
#pragma unroll
      for (int j = 0; j < 4; j++) acc[i][j] = 0.f;
    int cur = 0;
    mbar_wait(bar_q, 0);
    if (tid == 0) DBG(2);
#pragma unroll
    for (int j = 0; j < 4; j++) qf[j] = lds128(q_off + j * 64);

    int slot = 0;
    uint32_t par = 0;
    while (true) {
      mbar_wait(bar_full + 8 * slot, par);
      const int head = tile_s[slot] >> kHeadShift;
      while (cur != head) {
        if (tid == 0 && cur == 15) DBG(3);
        if (tid == 0) DBG(16 + cur);
        mbar_wait(bar_stg_empty, (cur & 1) ^ 1);
        l += __shfl_xor_sync(0xffffffffu, l, 1);
        l += __shfl_xor_sync(0xffffffffu, l, 2);
        float* stg = reinterpret_cast<float*>(smem + kOffStg) + warp * kWS + cls * kCS + (t & 1) * kHS +
                     (g ^ (cls << 1)) * 8;
#pragma unroll
        for (int i = 0; i < 4; i++) {
          *reinterpret_cast<float4*>(stg + (i >> 1) * 64 + (i & 1) * 4) =
              make_float4(acc[i][0], acc[i][1], acc[i][2], acc[i][3]);
#pragma unroll
          for (int j = 0; j < 4; j++) acc[i][j] = 0.f;
        }
        if ((lane & 23) == 0)
          reinterpret_cast<float2*>(smem + kOffMl)[warp * 2 + (lane >> 3)] = make_float2(mref, l);
        __syncwarp();
        if (lane == 0) mbar_arrive(bar_stg_full);
        mref = kNegBig;
        l = 0.f;
        cur++;
        if (cur < kHkv) {
          mbar_wait(bar_q + 8, 0);
#pragma unroll
          for (int j = 0; j < 4; j++) qf[j] = lds128(q_off + cur * 512 + j * 64);
        }
      }
      if (head == kHkv) break;

      const uint32_t st = sb + kOffRing + slot * kStageBytes;
      uint4 kf[4], vf[4];
#pragma unroll
      for (int j = 0; j < 4; j++) kf[j] = lds128(st + k_off + ((j * 64) ^ k_x));
      vf[0] = lds128(st + v_off);
      vf[1] = lds128(st + v_off + 256);
      vf[2] = lds128(st + v_off + 128);
      vf[3] = lds128(st + v_off + 256 + 128);

      float s[4][4];
#pragma unroll
      for (int j = 0; j < 4; j++) {
        s[j][0] = s[j][1] = s[j][2] = s[j][3] = 0.f;
        mma16816(s[j], qf[j].x, qf[j ^ 1].x, qf[j].y, qf[j ^ 1].y, kf[j].x, kf[j].y);
      }
#pragma unroll
      for (int j = 0; j < 4; j++) mma16816(s[j], qf[j].z, qf[j ^ 1].z, qf[j].w, qf[j ^ 1].w, kf[j].z, kf[j].w);
      const float s0 = (s[0][0] + s[1][0]) + (s[2][0] + s[3][0]);
      const float s1 = (s[0][3] + s[1][3]) + (s[2][3] + s[3][3]);

      asm volatile("" ::"r"(vf[0].x), "r"(vf[1].x), "r"(vf[2].x), "r"(vf[3].x) : "memory");
      __syncwarp();
      if (lane == 0) mbar_arrive(bar_empty + 8 * slot);

      float mx = fmaxf(s0, s1);
      mx = fmaxf(mx, __shfl_xor_sync(0xffffffffu, mx, 1));
      mx = fmaxf(mx, __shfl_xor_sync(0xffffffffu, mx, 2));
      const float mnew = fmaxf(mref, mx * c);
      const float alpha = ex2(mref - mnew);
      const float p0 = ex2(fmaf(s0, c, -mnew));
      const float p1 = ex2(fmaf(s1, c, -mnew));
      mref = mnew;
      l = fmaf(l, alpha, p0 + p1);
      const float ao = __shfl_sync(0xffffffffu, alpha, a_src);
      const uint32_t pk = pack_bf16(p0, p1);
      const uint32_t b0 = __byte_perm(pk, 0, sel0);
      const uint32_t b1 = __byte_perm(pk, 0, sel1);
#pragma unroll
      for (int i = 0; i < 4; i++)
#pragma unroll
        for (int j = 0; j < 4; j++) acc[i][j] *= ao;
      mma16816(acc[0], vf[0].x, vf[0].y, vf[1].x, vf[1].y, b0, b1);
      mma16816(acc[1], vf[0].z, vf[0].w, vf[1].z, vf[1].w, b0, b1);
      mma16816(acc[2], vf[2].x, vf[2].y, vf[3].x, vf[3].y, b0, b1);
      mma16816(acc[3], vf[2].z, vf[2].w, vf[3].z, vf[3].w, b0, b1);

      if (++slot == kS) { slot = 0; par ^= 1; }
    }

    float y[6];
#pragma unroll
    for (int i = 0; i < 6; i++) y[i] = 0.f;
    const uint32_t* wrow = reinterpret_cast<const uint32_t*>(smem + kOffWo) + (tid < kNRed ? tid : 0) * 3;
    auto rows = [&](int h, float2 o) {
      const uint32_t* r0 = wrow + h * 2 * (kD / 2);
      const uint32_t* r1 = r0 + kD / 2;
#pragma unroll
      for (int i = 0; i < 3; i++) {
        const uint32_t u0 = r0[i], u1 = r1[i];
        y[2 * i] = fmaf(o.x, bf_lo(u0), fmaf(o.y, bf_lo(u1), y[2 * i]));
        y[2 * i + 1] = fmaf(o.x, bf_hi(u0), fmaf(o.y, bf_hi(u1), y[2 * i + 1]));
      }
    };
    bar_sync(2, 256);
    mbar_wait(bar_wo, 0);
    if (tid == 0) DBG(4);
#pragma unroll 5
    for (int h = 0; h < kHkv - 1; h++) rows(h, reinterpret_cast<const float2*>(smem + kOffO)[h]);
    bar_sync(3, 256);
    rows(kHkv - 1, finish_o(reinterpret_cast<const float4*>(smem + kOffCmb) + (kHkv - 1) * 4));
    if (tid < kNRed) {
      uint4* dst = &g_scr.box[cta][1][0] + tid * 2;
      const uint32_t tag = tagbase + 16;
      st_pkt(dst, __float_as_uint(y[0]), __float_as_uint(y[1]), __float_as_uint(y[2]), tag);
      st_pkt(dst + 1, __float_as_uint(y[3]), __float_as_uint(y[4]), __float_as_uint(y[5]), tag);
    }
    if (tid == 0) DBG(7);
    return;
  }

  const int ht = tid - 128;
  {
    if (ht < 16) {
      const float* red = reinterpret_cast<const float*>(smem + kOffRed);
      float q0 = 0.f, q1 = 0.f;
#pragma unroll
      for (int w = 0; w < 8; w++) {
        const float2 v = *reinterpret_cast<const float2*>(red + w * 32 + ht * 2);
        q0 += v.x;
        q1 += v.y;
      }
      const uint64_t pkt = (uint64_t)pack_bf16(q0, q1) | ((uint64_t)tagbase << 32);
      asm volatile("st.relaxed.gpu.global.u64 [%0], %1;" ::"l"(&g_scr.qpk[cta * 16 + ht]), "l"(pkt) : "memory");
    }
    if (ht == 0) DBG(8);
    auto ld_q = [&](int i, uint64_t& v0, uint64_t& v1) {
      asm volatile("ld.relaxed.gpu.global.v2.u64 {%0,%1}, [%2];" : "=l"(v0), "=l"(v1) : "l"(&g_scr.qpk[2 * i]) : "memory");
    };
    uint2* q_s = reinterpret_cast<uint2*>(smem + kOffQ);
    if (ht < 64) {
      uint64_t v0, v1;
      for (int it = 0;; it++) {
        ld_q(ht, v0, v1);
        if (__all_sync(0xffffffffu, (uint32_t)(v0 >> 32) == tagbase && (uint32_t)(v1 >> 32) == tagbase)) break;
        __nanosleep(QPOLLNS);
        if (it > kPollLimit) __trap();
      }
      q_s[ht] = make_uint2((uint32_t)v0, (uint32_t)v1);
      __syncwarp();
      if (lane == 0) mbar_arrive(bar_q);
    }
    __nanosleep(2000);
    for (int it = 0;; it++) {
      uint64_t v[8][2];
      bool ok = true;
#pragma unroll
      for (int p = 0; p < 8; p++) ld_q(p * 128 + ht, v[p][0], v[p][1]);
#pragma unroll
      for (int p = 0; p < 8; p++) {
        ok = ok && (uint32_t)(v[p][0] >> 32) == tagbase && (uint32_t)(v[p][1] >> 32) == tagbase;
        if (p > 0 || ht >= 64) q_s[p * 128 + ht] = make_uint2((uint32_t)v[p][0], (uint32_t)v[p][1]);
      }
      if (__all_sync(0xffffffffu, ok)) break;
      __nanosleep(500);
      if (it > kPollLimit) __trap();
    }
    __syncwarp();
    if (lane == 0) mbar_arrive(bar_q + 8);
    if (ht == 0) DBG(9);
  }
  const int hh = ht >> 6;
  const float* stg = reinterpret_cast<const float*>(smem + kOffStg) + hh * kHS + (ht & 63) * 2;
  const float2* ml = reinterpret_cast<const float2*>(smem + kOffMl) + hh;
  int buf = 0;
  for (int h = 0; h < kHkv; h++) {
    mbar_wait(bar_stg_full, h & 1);
    const float2 m0 = ml[0], m1 = ml[2], m2 = ml[4], m3 = ml[6];
    float2 o[4];
#pragma unroll
    for (int w = 0; w < 4; w++) {
      const float2 u = *reinterpret_cast<const float2*>(stg + w * kWS);
      const float2 v = *reinterpret_cast<const float2*>(stg + w * kWS + kCS);
      o[w] = make_float2(u.x + v.x, u.y + v.y);
    }
    const float M = fmaxf(fmaxf(m0.x, m1.x), fmaxf(m2.x, m3.x));
    const float f0 = ex2(m0.x - M), f1 = ex2(m1.x - M), f2 = ex2(m2.x - M), f3 = ex2(m3.x - M);
    const float L = f0 * m0.y + f1 * m1.y + f2 * m2.y + f3 * m3.y;
    float oa = f0 * o[0].x + f1 * o[1].x + f2 * o[2].x + f3 * o[3].x;
    float ob = f0 * o[0].y + f1 * o[1].y + f2 * o[2].y + f3 * o[3].y;
    float lse = kNegBig;
    if (L > 0.f) {
      const float inv = rcp(L);
      oa *= inv;
      ob *= inv;
      lse = M + lg2(L);
    }
    const uint32_t tag = tagbase + h;
    st_pkt(&g_scr.box[cta][buf][ht], __float_as_uint(oa), __float_as_uint(ob), __float_as_uint(lse), tag);
    __syncwarp();
    if (lane == 0) mbar_arrive(bar_stg_empty);
    if (h == kHkv - 1 && ht == 0) DBG(5);
    uint4 pk;
    {
      const uint4* src = &g_scr.box[ht][buf][cta];
      if (h != kHkv - 1) {
        const long long t0 = clock64();
        while (__any_sync(0xffffffffu, clock64() - t0 < JOBDELAY)) __nanosleep(250);
      }
      for (int it = 0;; it++) {
        pk = ld_pkt(src);
        if (__all_sync(0xffffffffu, pk.w == tag)) break;
        if (h != kHkv - 1) __nanosleep(500);
        else if (POLLNS) __nanosleep(POLLNS);
        if (it > kPollLimit) __trap();
      }
      if (h == kHkv - 1) DBG2(0, ht);
    }
    const float e = __uint_as_float(pk.z);
    const float Mw = warp_max(e);
    float wgt = ex2(e - Mw);
    float sa = wgt * __uint_as_float(pk.x), sbb = wgt * __uint_as_float(pk.y);
#pragma unroll
    for (int o2 = 16; o2 > 0; o2 >>= 1) {
      sa += __shfl_xor_sync(0xffffffffu, sa, o2);
      sbb += __shfl_xor_sync(0xffffffffu, sbb, o2);
      wgt += __shfl_xor_sync(0xffffffffu, wgt, o2);
    }
    if (lane == 0) reinterpret_cast<float4*>(smem + kOffCmb)[h * 4 + (warp - 4)] = make_float4(Mw, sa, sbb, wgt);
    if (h == kHkv - 1) {
      bar_arrive(3, 256);
      if (ht == 0) DBG(6);
    }
    if (ht == 0) DBG(32 + h);
    bar_sync(1, 128);
    if (h < kHkv - 1 && ht == 0)
      reinterpret_cast<float2*>(smem + kOffO)[h] = finish_o(reinterpret_cast<const float4*>(smem + kOffCmb) + h * 4);
    if (h == kHkv - 2) bar_arrive(2, 256);
    if (++buf == 3) buf = 0;
  }
  if (cta == 0 && ht == 0) {
    g_scr.ticket = 0u;
    g_scr.epoch = epoch + 1u;
  }
  if (cta < kNRed) {
    const uint4* src = &g_scr.box[ht][1][0] + cta * 2;
    const uint32_t tag = tagbase + 16;
    uint4 a, b;
    for (int it = 0;; it++) {
      a = ld_pkt(src);
      b = ld_pkt(src + 1);
      if (__all_sync(0xffffffffu, a.w == tag && b.w == tag)) break;
      if (POLLNS) __nanosleep(POLLNS);
      if (it > kPollLimit) __trap();
    }
    DBG2(1, ht);
    if (ht == 0) DBG(10);
    float y[6] = {__uint_as_float(a.x), __uint_as_float(a.y), __uint_as_float(a.z),
                  __uint_as_float(b.x), __uint_as_float(b.y), __uint_as_float(b.z)};
#pragma unroll
    for (int o2 = 16; o2 > 0; o2 >>= 1) {
#pragma unroll
      for (int i = 0; i < 6; i++) y[i] += __shfl_xor_sync(0xffffffffu, y[i], o2);
    }
    float* red = reinterpret_cast<float*>(smem + kOffRed);
    if (lane == 0) {
#pragma unroll
      for (int i = 0; i < 6; i++) red[(warp - 4) * 8 + i] = y[i];
    }
    bar_sync(1, 128);
    if (ht < 3) {
      const float u = (red[2 * ht] + red[8 + 2 * ht]) + (red[16 + 2 * ht] + red[24 + 2 * ht]);
      const float v = (red[2 * ht + 1] + red[9 + 2 * ht]) + (red[17 + 2 * ht] + red[25 + 2 * ht]);
      reinterpret_cast<uint32_t*>(out)[cta * 3 + ht] = pack_bf16(u, v);
    }
    if (ht == 0) DBG(11);
  }
}

}

extern "C" void kernel_launch(void* const* d_in, const int* in_sizes, int n_in, void* d_out, int out_size) {
  (void)in_sizes; (void)n_in; (void)out_size;
  static bool configured = false;
  if (!configured) {
    cudaFuncSetAttribute(gqa::gqa_decode_kernel, cudaFuncAttributeMaxDynamicSharedMemorySize, gqa::kSmemBytes);
    configured = true;
  }
  gqa::gqa_decode_kernel<<<gqa::kG, gqa::kThreads, gqa::kSmemBytes, cudaStreamPerThread>>>(
      (const __nv_bfloat16*)d_in[0], (const __nv_bfloat16*)d_in[1], (const __nv_bfloat16*)d_in[2],
      (const __nv_bfloat16*)d_in[3], (const __nv_bfloat16*)d_in[4], (__nv_bfloat16*)d_out);
}
```

```cpp
#include <cuda_runtime.h>
#include <cuda_bf16.h>
#include <stdint.h>

namespace gqa {

constexpr int kD = 576;
constexpr int kHkv = 16;
constexpr int kSk = 65536;
constexpr int kDh = 128;
constexpr int kQ = 4096;
constexpr int kG = 128;
constexpr int kTP = 32;
constexpr int kTileBytes = kTP * kDh * 2;
constexpr int kStageBytes = 2 * kTileBytes + 128;
constexpr int kNTiles = kHkv * kSk / kTP;
constexpr int kHeadShift = 11;
constexpr int kEndTiles = 256;
constexpr int kGatherDelay = 9000;
constexpr int kThreads = 288;
constexpr int kWoRowBytes = kD * 2;
constexpr int kHS = 144;
constexpr int kWS = 2 * kHS;
constexpr int kStgFloats = 4 * kWS + 8 + 32;
constexpr int kNProj = 96;
constexpr int kYStride = 24;

template <int S, int W, int WE>
struct Cfg {
  static constexpr int kS = S, kW = W, kWEnd = WE;
  static_assert(W < S && WE < S && S <= 16, "window");
  static constexpr int kOffWo = S * kStageBytes;
  static constexpr int kOffQ = kOffWo + 32 * kWoRowBytes;
  static constexpr int kOffStg = kOffQ + kQ * 2;
  static constexpr int kOffRed = kOffStg + 2 * kStgFloats * 4;
  static constexpr int kOffO = kOffRed + 1024;
  static constexpr int kOffTile = kOffO + 128;
  static constexpr int kOffBar = kOffTile + 64;
  static constexpr int kNumBars = 2 * S + 9;
  static constexpr int kSmemBytes = kOffBar + kNumBars * 8;
};

struct __align__(128) Scratch {
  unsigned int ticket;
  unsigned int pad0[63];
  unsigned int epoch;
  unsigned int pad1[63];
  uint2 qpk[kQ / 2];
  uint4 box[2][kG][kG];
  float4 yacc[kNProj * kYStride];
};
__device__ Scratch g_scr;

constexpr long long kSpinLimit = 4000000000LL;
constexpr int kPollLimit = 1 << 22;
constexpr int kSmemPollLimit = 1 << 27;

__device__ __forceinline__ void mbar_init(uint32_t bar, int cnt) {
  asm volatile("mbarrier.init.shared.b64 [%0], %1;" ::"r"(bar), "r"(cnt) : "memory");
}
__device__ __forceinline__ void mbar_expect_tx(uint32_t bar, uint32_t bytes) {
  asm volatile("mbarrier.arrive.expect_tx.shared.b64 _, [%0], %1;" ::"r"(bar), "r"(bytes) : "memory");
}
__device__ __forceinline__ void mbar_arrive(uint32_t bar) {
  asm volatile("mbarrier.arrive.shared.b64 _, [%0];" ::"r"(bar) : "memory");
}
__device__ __forceinline__ bool mbar_try(uint32_t bar, uint32_t parity) {
  uint32_t ok;
  asm volatile(
      "{\n.reg .pred p;\n"
      "mbarrier.try_wait.parity.shared.b64 p, [%1], %2;\n"
      "selp.u32 %0, 1, 0, p;\n}"
      : "=r"(ok)
      : "r"(bar), "r"(parity)
      : "memory");
  return ok != 0;
}
__device__ __noinline__ void mbar_wait_slow(uint32_t bar, uint32_t parity) {
  const long long t0 = clock64();
  while (!mbar_try(bar, parity)) {
    if (clock64() - t0 > kSpinLimit) __trap();
  }
}
__device__ __forceinline__ void mbar_wait(uint32_t bar, uint32_t parity) {
  if (mbar_try(bar, parity)) return;
  if (mbar_try(bar, parity)) return;
  mbar_wait_slow(bar, parity);
}
__device__ __forceinline__ void bulk_load(uint32_t dst, const void* src, uint32_t bytes, uint32_t bar,
                                          uint64_t pol) {
  asm volatile(
      "cp.async.bulk.shared::cluster.global.mbarrier::complete_tx::bytes.L2::cache_hint [%0], [%1], %2, [%3], %4;"
      ::"r"(dst), "l"(src), "r"(bytes), "r"(bar), "l"(pol)
      : "memory");
}
__device__ __forceinline__ uint4 lds128(uint32_t a) {
  uint4 v;
  asm volatile("ld.shared.v4.u32 {%0,%1,%2,%3}, [%4];" : "=r"(v.x), "=r"(v.y), "=r"(v.z), "=r"(v.w) : "r"(a) : "memory");
  return v;
}
__device__ __forceinline__ float2 lds64f(uint32_t a) {
  float2 v;
  asm volatile("ld.shared.v2.f32 {%0,%1}, [%2];" : "=f"(v.x), "=f"(v.y) : "r"(a) : "memory");
  return v;
}
__device__ __forceinline__ void sts128(uint32_t a, float x, float y, float z, float w) {
  asm volatile("st.shared.v4.f32 [%0], {%1,%2,%3,%4};" ::"r"(a), "f"(x), "f"(y), "f"(z), "f"(w) : "memory");
}
__device__ __forceinline__ void sts32(uint32_t a, float x) {
  asm volatile("st.shared.f32 [%0], %1;" ::"r"(a), "f"(x) : "memory");
}
__device__ __forceinline__ void mma16816(float (&c)[4], uint32_t a0, uint32_t a1, uint32_t a2, uint32_t a3,
                                         uint32_t b0, uint32_t b1) {
  asm volatile(
      "mma.sync.aligned.m16n8k16.row.col.f32.bf16.bf16.f32 {%0,%1,%2,%3}, {%4,%5,%6,%7}, {%8,%9}, {%0,%1,%2,%3};"
      : "+f"(c[0]), "+f"(c[1]), "+f"(c[2]), "+f"(c[3])
      : "r"(a0), "r"(a1), "r"(a2), "r"(a3), "r"(b0), "r"(b1));
}
__device__ __forceinline__ float ex2(float x) {
  float y;
  asm("ex2.approx.ftz.f32 %0, %1;" : "=f"(y) : "f"(x));
  return y;
}
__device__ __forceinline__ float lg2(float x) {
  float y;
  asm("lg2.approx.ftz.f32 %0, %1;" : "=f"(y) : "f"(x));
  return y;
}
__device__ __forceinline__ float rcp(float x) {
  float y;
  asm("rcp.approx.ftz.f32 %0, %1;" : "=f"(y) : "f"(x));
  return y;
}
__device__ __forceinline__ float warp_max(float v) {
  int k = __float_as_int(v);
  k ^= (k >> 31) & 0x7fffffff;
  k = __reduce_max_sync(0xffffffffu, k);
  k ^= (k >> 31) & 0x7fffffff;
  return __int_as_float(k);
}
__device__ __forceinline__ void st_pkt(uint4* p, uint32_t x, uint32_t y, uint32_t z, uint32_t w, bool urgent) {
  const uint64_t lo = (uint64_t)x | ((uint64_t)y << 32), hi = (uint64_t)z | ((uint64_t)w << 32);
  if (urgent)
    asm volatile("{\n.reg .b128 v, d;\nmov.b128 v, {%1, %2};\natom.relaxed.gpu.global.exch.b128 d, [%0], v;\n}"
                 ::"l"(p), "l"(lo), "l"(hi) : "memory");
  else
    asm volatile("{\n.reg .b128 v;\nmov.b128 v, {%1, %2};\nst.relaxed.gpu.global.b128 [%0], v;\n}"
                 ::"l"(p), "l"(lo), "l"(hi) : "memory");
}
__device__ __forceinline__ uint4 ld_pkt(const uint4* p) {
  uint64_t lo, hi;
  asm volatile("{\n.reg .b128 v;\nld.relaxed.gpu.global.b128 v, [%2];\nmov.b128 {%0, %1}, v;\n}"
               : "=l"(lo), "=l"(hi)
               : "l"(p)
               : "memory");
  return make_uint4((uint32_t)lo, (uint32_t)(lo >> 32), (uint32_t)hi, (uint32_t)(hi >> 32));
}
__device__ __forceinline__ float4* yacc_ptr(Scratch* scr, int i) { return &scr->yacc[(i >> 1) * kYStride + (i & 1)]; }
__device__ __forceinline__ unsigned int draw_ticket(unsigned int* p) {
  unsigned int v;
  asm volatile("atom.relaxed.gpu.global.inc.u32 %0, [%1], 0x7fffffff;" : "=r"(v) : "l"(p) : "memory");
  return v;
}
__device__ __forceinline__ float4 atom_add4(float4* p, float a, float b, float c, float d) {
  float4 o;
  asm volatile("atom.relaxed.gpu.global.add.v4.f32 {%0,%1,%2,%3}, [%4], {%5,%6,%7,%8};"
               : "=f"(o.x), "=f"(o.y), "=f"(o.z), "=f"(o.w)
               : "l"(p), "f"(a), "f"(b), "f"(c), "f"(d)
               : "memory");
  return o;
}
__device__ __forceinline__ void bar_sync(int id, int n) { asm volatile("bar.sync %0, %1;" ::"r"(id), "r"(n) : "memory"); }
__device__ __forceinline__ void bar_arrive(int id, int n) { asm volatile("bar.arrive %0, %1;" ::"r"(id), "r"(n) : "memory"); }
__device__ __forceinline__ float bf_lo(uint32_t v) { return __uint_as_float(v << 16); }
__device__ __forceinline__ float bf_hi(uint32_t v) { return __uint_as_float(v & 0xffff0000u); }
__device__ __forceinline__ uint32_t pack_bf16(float lo, float hi) {
  uint32_t r;
  asm("cvt.rn.bf16x2.f32 %0, %1, %2;" : "=r"(r) : "f"(hi), "f"(lo));
  return r;
}

constexpr float kNegBig = -3.0e38f;

template <class C, int kMinBlocks>
__global__ void __launch_bounds__(kThreads, kMinBlocks)
gqa_decode_kernel(const __nv_bfloat16* __restrict__ x, const __nv_bfloat16* __restrict__ kc,
                  const __nv_bfloat16* __restrict__ vc, const __nv_bfloat16* __restrict__ wq,
                  const __nv_bfloat16* __restrict__ wo, __nv_bfloat16* __restrict__ out, Scratch* __restrict__ scr) {
  constexpr int kS = C::kS, kW = C::kW;
  extern __shared__ __align__(128) unsigned char smem[];
  const uint32_t sb = (uint32_t)__cvta_generic_to_shared(smem);
  const int tid = threadIdx.x, warp = tid >> 5, lane = tid & 31;
  const int cta = blockIdx.x;

  const uint32_t bar_full = sb + C::kOffBar;
  const uint32_t bar_empty = bar_full + 8 * kS;
  const uint32_t bar_q = bar_empty + 8 * kS;
  const uint32_t bar_sent = bar_q + 16;
  const uint32_t bar_job = bar_sent + 8;
  const uint32_t bar_o = bar_job + 8;
  const uint32_t bar_wo = bar_o + 8;
  volatile uint32_t* tile_s = reinterpret_cast<volatile uint32_t*>(smem + C::kOffTile);

  if (warp == 8) {
    uint64_t pol = 0;
    const char* kb = reinterpret_cast<const char*>(kc);
    const char* vb = reinterpret_cast<const char*>(vc);
    uint32_t pseq = 1u << 16;
    auto issue = [&](int slot, int tile) {
      tile_s[slot] = pseq | (uint32_t)tile;
      pseq += 1u << 16;
      const uint32_t fb = bar_full + 8 * slot;
      const uint32_t dst = sb + slot * kStageBytes;
      const size_t off = (size_t)tile * kTileBytes;
      mbar_expect_tx(fb, 2 * kTileBytes);
      bulk_load(dst, kb + off, kTileBytes, fb, pol);
      bulk_load(dst + kTileBytes, vb + off, kTileBytes / 2, fb, pol);
      bulk_load(dst + kTileBytes + kTileBytes / 2 + 32, vb + off + kTileBytes / 2, kTileBytes / 2, fb, pol);
    };
    unsigned int ticket = 0;
    if (lane == 0) {
      asm volatile("createpolicy.fractional.L2::evict_first.b64 %0, 1.0;" : "=l"(pol));
#pragma unroll
      for (int i = 0; i < kW; i++) mbar_init(bar_full + 8 * i, 1);
      asm volatile("fence.mbarrier_init.release.cluster;" ::: "memory");
#pragma unroll
      for (int i = 0; i < kW; i++) issue(i, cta + i * kG);
#pragma unroll
      for (int i = kW; i < C::kNumBars; i++) {
        mbar_init(bar_full + 8 * i, i < kS ? 1 : i < 2 * kS ? 4 : i == 2 * kS ? 2 : i <= 2 * kS + 2 ? 4 : 1);
      }
      asm volatile("fence.mbarrier_init.release.cluster;" ::: "memory");
      reinterpret_cast<volatile unsigned long long*>(smem + C::kOffO)[kHkv - 1] = 0ull;
#pragma unroll
      for (int i = kW; i < kS; i++) tile_s[i] = 0u;
      ticket = draw_ticket(&scr->ticket);
    }
    __syncwarp();
    bar_arrive(0, kThreads);
    if (lane == 0) {
      int n_slot = kW, w_slot = 0, inflight = kW;
      uint32_t n_par = 0, w_par = 0;
      auto land = [&]() {
        mbar_wait(bar_full + 8 * w_slot, w_par);
        if (++w_slot == kS) { w_slot = 0; w_par ^= 1; }
        inflight--;
      };
      while (true) {
        const int tile = (int)ticket + kW * kG;
        if (tile >= kNTiles) break;
        if (inflight >= (tile >= kNTiles - kEndTiles ? C::kWEnd : kW)) land();
        mbar_wait(bar_empty + 8 * n_slot, n_par ^ 1);
        ticket = draw_ticket(&scr->ticket);
        issue(n_slot, tile);
        inflight++;
        if (++n_slot == kS) { n_slot = 0; n_par ^= 1; }
      }
      mbar_wait(bar_empty + 8 * n_slot, n_par ^ 1);
      tile_s[n_slot] = pseq | (uint32_t)kNTiles;
      while (inflight > 1) land();
      const char* wob = reinterpret_cast<const char*>(wo) + (size_t)(2 * cta) * kWoRowBytes;
#pragma unroll 1
      for (int h = 0; h < kHkv; h++) {
        const uint32_t wb = bar_wo + 8 * (h >> 2);
        if ((h & 3) == 0) mbar_expect_tx(wb, 8 * kWoRowBytes);
        bulk_load(sb + C::kOffWo + h * 2 * kWoRowBytes, wob + (size_t)h * 256 * kWoRowBytes, 2 * kWoRowBytes, wb, pol);
      }
    }
    return;
  }

  unsigned int epoch;
  {
    const int r = tid >> 2, cq = tid & 3;
    const char* wp = reinterpret_cast<const char*>(wq) + (size_t)r * (kQ * 2) + cta * 64 + cq * 16;
    uint4 w[9];
    unsigned short xv[9];
    asm volatile("ld.relaxed.gpu.global.u32 %0, [%1];" : "=r"(epoch) : "l"(&scr->epoch) : "memory");
#pragma unroll
    for (int k = 0; k < 9; k++) {
      asm volatile("ld.global.nc.L1::no_allocate.L2::256B.v4.u32 {%0,%1,%2,%3}, [%4];"
                   : "=r"(w[k].x), "=r"(w[k].y), "=r"(w[k].z), "=r"(w[k].w)
                   : "l"(wp + (size_t)k * 64 * (kQ * 2)));
    }
#pragma unroll
    for (int k = 0; k < 9; k++) asm volatile("ld.global.nc.u16 %0, [%1];" : "=h"(xv[k]) : "l"(x + r + 64 * k));
    float a[8];
#pragma unroll
    for (int i = 0; i < 8; i++) a[i] = 0.f;
#pragma unroll
    for (int k = 0; k < 9; k++) {
      const float xf = __uint_as_float((uint32_t)xv[k] << 16);
      a[0] = fmaf(xf, bf_lo(w[k].x), a[0]);
      a[1] = fmaf(xf, bf_hi(w[k].x), a[1]);
      a[2] = fmaf(xf, bf_lo(w[k].y), a[2]);
      a[3] = fmaf(xf, bf_hi(w[k].y), a[3]);
      a[4] = fmaf(xf, bf_lo(w[k].z), a[4]);
      a[5] = fmaf(xf, bf_hi(w[k].z), a[5]);
      a[6] = fmaf(xf, bf_lo(w[k].w), a[6]);
      a[7] = fmaf(xf, bf_hi(w[k].w), a[7]);
    }
#pragma unroll
    for (int o = 4; o < 32; o <<= 1) {
#pragma unroll
      for (int i = 0; i < 8; i++) a[i] += __shfl_xor_sync(0xffffffffu, a[i], o);
    }
    float* red = reinterpret_cast<float*>(smem + C::kOffRed);
    if (lane < 4) {
      *reinterpret_cast<float4*>(red + warp * 32 + lane * 8) = make_float4(a[0], a[1], a[2], a[3]);
      *reinterpret_cast<float4*>(red + warp * 32 + lane * 8 + 4) = make_float4(a[4], a[5], a[6], a[7]);
    }
    bar_sync(0, kThreads);
  }
  const uint32_t tagbase = (epoch + 1u) * 32u;

  if (warp < 4) {
    const int g = lane >> 2, t = lane & 3;
    const float kScale = 0.08838834764831845f;
    const float c = 1.4426950408889634f;
    const uint32_t selp0 = (g & 1) ? 0x1044 : 0x4410, selp1 = (g & 1) ? 0x3244 : 0x4432;
    uint32_t selA0 = g < 4 ? selp0 : 0x4444, selA1 = g < 4 ? 0x4444 : selp0;
    uint32_t selB0 = g < 4 ? selp1 : 0x4444, selB1 = g < 4 ? 0x4444 : selp1;
    const int k_row = 8 * (g >> 1) + 2 * warp + (g & 1);
    uint32_t k_a = sb + k_row * 256 + t * 16 + (g & 1) * 64;
    uint32_t k_b = sb + k_row * 256 + t * 16 + ((g & 1) ^ 1) * 64;
    uint32_t v_a = sb + kTileBytes + (8 * t + 2 * warp) * 256 + (t >> 1) * 32 + g * 16;
    const uint32_t q_off = sb + C::kOffQ + ((g >> 1) & 1) * 256 + t * 16;
    uint32_t st_w = sb + C::kOffStg + (warp * kWS + (t & 1) * kHS + g * 8 + (t >> 1) * 4) * 4;
    uint32_t st_r = sb + C::kOffStg + ((tid >> 6) * kHS + (tid & 63) * 2) * 4;
    uint32_t ml_w = sb + C::kOffStg + (4 * kWS + 8 + ((g >> 1) & 1) * 16 + warp * 4 + t) * 4;
    uint32_t ml_r = sb + C::kOffStg + (4 * kWS + (tid >> 6) * 4) * 4;
    uint4* pkt_dst = &scr->box[0][cta][tid];
    asm volatile("" : "+r"(selA0), "+r"(selA1), "+r"(selB0), "+r"(selB1), "+r"(k_a), "+r"(k_b), "+r"(v_a));
    asm volatile("" : "+r"(st_w), "+r"(st_r), "+r"(ml_w), "+r"(ml_r), "+l"(pkt_dst));

    uint32_t qa[8][4];
    auto load_q = [&](int h) {
      uint4 qf[4];
#pragma unroll
      for (int j = 0; j < 4; j++) qf[j] = lds128(q_off + h * 512 + j * 64);
#pragma unroll
      for (int j = 0; j < 4; j++) {
        qa[j][0] = qf[j].x; qa[j][1] = qf[j ^ 1].x; qa[j][2] = qf[j].y; qa[j][3] = qf[j ^ 1].y;
        qa[4 + j][0] = qf[j].z; qa[4 + j][1] = qf[j ^ 1].z; qa[4 + j][2] = qf[j].w; qa[4 + j][3] = qf[j ^ 1].w;
      }
#pragma unroll
      for (int j = 0; j < 8; j++) asm volatile("" : "+r"(qa[j][0]), "+r"(qa[j][1]), "+r"(qa[j][2]), "+r"(qa[j][3]));
    };
    float acc[4][4];
    float mref = kNegBig, l = 0.f;
#pragma unroll
    for (int i = 0; i < 4; i++)
#pragma unroll
      for (int j = 0; j < 4; j++) acc[i][j] = 0.f;
    int cur = 0;
    mbar_wait(bar_q, 0);
    load_q(0);

    int slot = 0;
    uint32_t par = 0, seq = 1;
    uint32_t info = tile_s[0];
    while (true) {
      const int head = (int)(info & 0xffffu) >> kHeadShift;
      while (cur != head) {
        const uint32_t so = (cur & 1) * (kStgFloats * 4);
        const bool job_ok = mbar_try(bar_job, (cur & 1) ^ 1);
        sts128(st_w + so, acc[0][0] + acc[1][0], acc[0][1] + acc[1][1], acc[0][2] + acc[1][2], acc[0][3] + acc[1][3]);
        sts128(st_w + so + 256, acc[2][0] + acc[3][0], acc[2][1] + acc[3][1], acc[2][2] + acc[3][2],
               acc[2][3] + acc[3][3]);
        if ((g & 5) == 0) {
          sts32(ml_w + so, l);
          if (t == 0) sts32(sb + C::kOffStg + so + (4 * kWS + (g >> 1) * 4 + warp) * 4, mref);
        }
        if (!job_ok) mbar_wait(bar_job, (cur & 1) ^ 1);
        bar_sync(1, 128);
        {
          const uint4 mm = lds128(ml_r + so);
          float2 o[4];
          float lw[4];
#pragma unroll
          for (int w = 0; w < 4; w++) {
            o[w] = lds64f(st_r + so + w * (kWS * 4));
            const uint4 u = lds128(ml_r + so + 32 + (tid >> 6) * 48 + w * 16);
            lw[w] = (__uint_as_float(u.x) + __uint_as_float(u.y)) + (__uint_as_float(u.z) + __uint_as_float(u.w));
          }
          const float m0 = __uint_as_float(mm.x), m1 = __uint_as_float(mm.y);
          const float m2 = __uint_as_float(mm.z), m3 = __uint_as_float(mm.w);
          const float M = fmaxf(fmaxf(m0, m1), fmaxf(m2, m3));
          const float f0 = ex2(m0 - M), f1 = ex2(m1 - M), f2 = ex2(m2 - M), f3 = ex2(m3 - M);
          const float L = (f0 * lw[0] + f1 * lw[1]) + (f2 * lw[2] + f3 * lw[3]);
          const float inv = L > 0.f ? rcp(L) : 0.f;
          const float oa = ((f0 * o[0].x + f1 * o[1].x) + (f2 * o[2].x + f3 * o[3].x)) * inv;
          const float ob = ((f0 * o[0].y + f1 * o[1].y) + (f2 * o[2].y + f3 * o[3].y)) * inv;
          const float lse = L > 0.f ? M + lg2(L) : kNegBig;
          st_pkt(pkt_dst + (cur & 1) * (kG * kG), __float_as_uint(oa), __float_as_uint(ob), __float_as_uint(lse),
                 tagbase + cur, cur == kHkv - 1);
        }
        if (lane == 0) mbar_arrive(bar_sent);
#pragma unroll
        for (int i = 0; i < 4; i++)
#pragma unroll
          for (int j = 0; j < 4; j++) acc[i][j] = 0.f;
        mref = kNegBig;
        l = 0.f;
        cur++;
        if (cur < kHkv) {
          mbar_wait(bar_q + 8, 0);
          load_q(cur);
        }
      }
      if (head == kHkv) break;

      const uint32_t so = slot * kStageBytes;
      const uint32_t eb = bar_empty + 8 * slot;
      mbar_wait(bar_full + 8 * slot, par);
      uint4 kf[4], vf[4];
      kf[0] = lds128(k_a + so);
      kf[1] = lds128(k_b + so);
      kf[2] = lds128(k_a + so + 128);
      kf[3] = lds128(k_b + so + 128);
      vf[0] = lds128(v_a + so);
      vf[1] = lds128(v_a + so + 256);
      vf[2] = lds128(v_a + so + 128);
      vf[3] = lds128(v_a + so + 256 + 128);
      if (++slot == kS) { slot = 0; par ^= 1; }
      seq++;
      info = tile_s[slot];

      float s[4][4];
#pragma unroll
      for (int j = 0; j < 4; j++) {
        s[j][0] = s[j][1] = s[j][2] = s[j][3] = 0.f;
        mma16816(s[j], qa[j][0], qa[j][1], qa[j][2], qa[j][3], kf[j].x, kf[j].y);
      }
#pragma unroll
      for (int j = 0; j < 4; j++)
        mma16816(s[j], qa[4 + j][0], qa[4 + j][1], qa[4 + j][2], qa[4 + j][3], kf[j].z, kf[j].w);
      uint32_t sp = pack_bf16((s[0][0] + s[1][0]) + (s[2][0] + s[3][0]), (s[0][3] + s[1][3]) + (s[2][3] + s[3][3]));
      sp = pack_bf16(bf_lo(sp) * kScale, bf_hi(sp) * kScale);
      const float s0 = bf_lo(sp), s1 = bf_hi(sp);

      float mx = fmaxf(s0, s1) * c;
      if (__any_sync(0xffffffffu, mx > mref)) {
        mx = fmaxf(mx, __shfl_xor_sync(0xffffffffu, mx, 1));
        mx = fmaxf(mx, __shfl_xor_sync(0xffffffffu, mx, 2));
        const float mnew = fmaxf(mref, mx);
        const float alpha = ex2(mref - mnew);
        mref = mnew;
        l *= alpha;
        const float ao = __shfl_sync(0xffffffffu, alpha, (t & 1) * 8);
#pragma unroll
        for (int i = 0; i < 4; i++)
#pragma unroll
          for (int j = 0; j < 4; j++) acc[i][j] *= ao;
      }
      const float p0 = ex2(fmaf(s0, c, -mref));
      const float p1 = ex2(fmaf(s1, c, -mref));
      l += p0 + p1;
      const uint32_t pk = pack_bf16(p0, p1);
      const uint32_t bA0 = __byte_perm(pk, 0, selA0), bA1 = __byte_perm(pk, 0, selA1);
      const uint32_t bB0 = __byte_perm(pk, 0, selB0), bB1 = __byte_perm(pk, 0, selB1);
      mma16816(acc[0], vf[0].x, vf[0].y, vf[0].z, vf[0].w, bA0, bA1);
      mma16816(acc[1], vf[1].x, vf[1].y, vf[1].z, vf[1].w, bB0, bB1);
      mma16816(acc[2], vf[2].x, vf[2].y, vf[2].z, vf[2].w, bA0, bA1);
      mma16816(acc[3], vf[3].x, vf[3].y, vf[3].z, vf[3].w, bB0, bB1);
      __syncwarp();
      if (lane == 0) mbar_arrive(eb);

      for (int it = 0; (info >> 16) != seq; it++) {
        info = tile_s[slot];
        if (it > kSmemPollLimit) __trap();
      }
    }
    return;
  }

  const int ht = tid - 128;
  {
    if (ht < 16) {
      const float* red = reinterpret_cast<const float*>(smem + C::kOffRed);
      float q0 = 0.f, q1 = 0.f;
#pragma unroll
      for (int w = 0; w < 8; w++) {
        const float2 v = *reinterpret_cast<const float2*>(red + w * 32 + ht * 2);
        q0 += v.x;
        q1 += v.y;
      }
      const uint64_t pkt = (uint64_t)pack_bf16(q0, q1) | ((uint64_t)tagbase << 32);
      asm volatile("st.relaxed.gpu.global.u64 [%0], %1;" ::"l"(&scr->qpk[cta * 16 + ht]), "l"(pkt) : "memory");
    }
    auto ld_q = [&](int i, uint64_t& v0, uint64_t& v1) {
      asm volatile("ld.relaxed.gpu.global.v2.u64 {%0,%1}, [%2];" : "=l"(v0), "=l"(v1) : "l"(&scr->qpk[2 * i]) : "memory");
    };
    uint2* q_s = reinterpret_cast<uint2*>(smem + C::kOffQ);
    if (ht < 64) {
      uint64_t v0, v1;
      for (int it = 0;; it++) {
        ld_q(ht, v0, v1);
        if (__all_sync(0xffffffffu, (uint32_t)(v0 >> 32) == tagbase && (uint32_t)(v1 >> 32) == tagbase)) break;
        __nanosleep(100);
        if (it > kPollLimit) __trap();
      }
      q_s[ht] = make_uint2((uint32_t)v0, (uint32_t)v1);
      __syncwarp();
      if (lane == 0) mbar_arrive(bar_q);
    }
    __nanosleep(2000);
    for (int it = 0;; it++) {
      uint64_t v[8][2];
      bool ok = true;
#pragma unroll
      for (int p = 0; p < 8; p++) ld_q(p * 128 + ht, v[p][0], v[p][1]);
#pragma unroll
      for (int p = 0; p < 8; p++) {
        ok = ok && (uint32_t)(v[p][0] >> 32) == tagbase && (uint32_t)(v[p][1] >> 32) == tagbase;
        if (p > 0 || ht >= 64) q_s[p * 128 + ht] = make_uint2((uint32_t)v[p][0], (uint32_t)v[p][1]);
      }
      if (__all_sync(0xffffffffu, ok)) break;
      __nanosleep(500);
      if (it > kPollLimit) __trap();
    }
    __syncwarp();
    if (lane == 0) mbar_arrive(bar_q + 8);
  }

  if (warp != 4) {
    const int pt = tid - 160;
    float y[6];
#pragma unroll
    for (int i = 0; i < 6; i++) y[i] = 0.f;
    const uint32_t* wrow = reinterpret_cast<const uint32_t*>(smem + C::kOffWo) + pt * 3;
    auto fma_rows = [&](uint32_t o, const uint32_t (&u)[6]) {
      const float ox = bf_lo(o), oy = bf_hi(o);
#pragma unroll
      for (int i = 0; i < 3; i++) {
        y[2 * i] = fmaf(ox, bf_lo(u[i]), fmaf(oy, bf_lo(u[3 + i]), y[2 * i]));
        y[2 * i + 1] = fmaf(ox, bf_hi(u[i]), fmaf(oy, bf_hi(u[3 + i]), y[2 * i + 1]));
      }
    };
    mbar_wait(bar_o, 0);
    uint32_t u[4][6];
#pragma unroll 1
    for (int ch = 0; ch < 4; ch++) {
      const uint4 oa = lds128(sb + C::kOffO + ch * 32), ob = lds128(sb + C::kOffO + ch * 32 + 16);
      mbar_wait(bar_wo + 8 * ch, 0);
#pragma unroll
      for (int k = 0; k < 4; k++) {
#pragma unroll
        for (int i = 0; i < 3; i++) {
          u[k][i] = wrow[(ch * 4 + k) * kD + i];
          u[k][3 + i] = wrow[(ch * 4 + k) * kD + kD / 2 + i];
        }
      }
      fma_rows(oa.x, u[0]);
      fma_rows(oa.z, u[1]);
      fma_rows(ob.x, u[2]);
      if (ch < 3) fma_rows(ob.z, u[3]);
    }
    {
      unsigned long long o15;
      for (int it = 0;; it++) {
        o15 = reinterpret_cast<const volatile unsigned long long*>(smem + C::kOffO)[kHkv - 1];
        if (o15 >> 32) break;
        if (it > kSmemPollLimit) __trap();
      }
      fma_rows((uint32_t)o15, u[3]);
    }
    const float4 a = atom_add4(yacc_ptr(scr, pt), y[0], y[1], y[2], 1.0f);
    const float4 b = atom_add4(yacc_ptr(scr, kNProj + pt), y[3], y[4], y[5], 1.0f);
    unsigned short* op = reinterpret_cast<unsigned short*>(out) + pt * 6;
    if (a.w == (float)(kG - 1)) {
      *reinterpret_cast<uint32_t*>(op) = pack_bf16(a.x + y[0], a.y + y[1]);
      op[2] = (unsigned short)pack_bf16(a.z + y[2], 0.f);
    }
    if (b.w == (float)(kG - 1)) {
      op[3] = (unsigned short)pack_bf16(b.x + y[3], 0.f);
      *reinterpret_cast<uint32_t*>(op + 4) = pack_bf16(b.y + y[4], b.z + y[5]);
    }
    return;
  }

  volatile unsigned long long* o_s = reinterpret_cast<volatile unsigned long long*>(smem + C::kOffO);
  for (int h = 0; h < kHkv; h++) {
    const bool last = h == kHkv - 1;
    mbar_wait(bar_sent, h & 1);
    if (!last) {
      const long long t0 = clock64();
      while (__any_sync(0xffffffffu, clock64() - t0 < kGatherDelay)) __nanosleep(250);
    }
    const uint32_t tag = tagbase + h;
    const uint4* src = &scr->box[h & 1][lane][cta];
    uint4 pk[4];
#pragma unroll
    for (int k = 0; k < 4; k++) pk[k].w = tag - 1u;
    for (int it = 0;; it++) {
#pragma unroll
      for (int k = 0; k < 4; k++)
        if (pk[k].w != tag) pk[k] = ld_pkt(src + k * 32 * kG);
      if (__all_sync(0xffffffffu, pk[0].w == tag && pk[1].w == tag && pk[2].w == tag && pk[3].w == tag)) break;
      if (!last) __nanosleep(500);
      if (it > kPollLimit) __trap();
    }
    const float e0 = __uint_as_float(pk[0].z), e1 = __uint_as_float(pk[1].z);
    const float e2 = __uint_as_float(pk[2].z), e3 = __uint_as_float(pk[3].z);
    const float M = warp_max(fmaxf(fmaxf(e0, e1), fmaxf(e2, e3)));
    const float w0 = ex2(e0 - M), w1 = ex2(e1 - M), w2 = ex2(e2 - M), w3 = ex2(e3 - M);
    float sa = (w0 * __uint_as_float(pk[0].x) + w1 * __uint_as_float(pk[1].x)) +
               (w2 * __uint_as_float(pk[2].x) + w3 * __uint_as_float(pk[3].x));
    float sc = (w0 * __uint_as_float(pk[0].y) + w1 * __uint_as_float(pk[1].y)) +
               (w2 * __uint_as_float(pk[2].y) + w3 * __uint_as_float(pk[3].y));
    float sw = (w0 + w1) + (w2 + w3);
#pragma unroll
    for (int o2 = 16; o2 > 0; o2 >>= 1) {
      sa += __shfl_xor_sync(0xffffffffu, sa, o2);
      sc += __shfl_xor_sync(0xffffffffu, sc, o2);
      sw += __shfl_xor_sync(0xffffffffu, sw, o2);
    }
    if (h == kHkv - 3 && cta == 1) {
#pragma unroll
      for (int k = 0; k < 6; k++) *yacc_ptr(scr, k * 32 + lane) = make_float4(0.f, 0.f, 0.f, 0.f);
      __threadfence();
      __syncwarp();
    }
    if (lane == 0) {
      const float inv = rcp(sw);
      o_s[h] = (unsigned long long)pack_bf16(sa * inv, sc * inv) | (1ull << 32);
      if (!last) mbar_arrive(bar_job);
      if (h == kHkv - 2) mbar_arrive(bar_o);
    }
  }
  if (cta == 0 && lane == 0) {
    scr->ticket = 0u;
    scr->epoch = epoch + 1u;
  }
}

using CfgMain = Cfg<8, 3, 6>;
using CfgSmall = Cfg<3, 2, 2>;
static_assert(CfgMain::kSmemBytes <= 232448 && CfgSmall::kSmemBytes <= 113 * 1024, "smem");

}

extern "C" void kernel_launch(void* const* d_in, const int* in_sizes, int n_in, void* d_out, int out_size) {
  (void)in_sizes; (void)n_in; (void)out_size;
  using namespace gqa;
  static Scratch* scr = nullptr;
  static bool small = false;
  if (!scr) {
    int dev = 0, sms = 0;
    cudaGetDevice(&dev);
    cudaDeviceGetAttribute(&sms, cudaDevAttrMultiProcessorCount, dev);
    small = sms < kG;
    cudaFuncSetAttribute(gqa_decode_kernel<CfgMain, 1>, cudaFuncAttributeMaxDynamicSharedMemorySize,
                         CfgMain::kSmemBytes);
    cudaFuncSetAttribute(gqa_decode_kernel<CfgSmall, 2>, cudaFuncAttributeMaxDynamicSharedMemorySize,
                         CfgSmall::kSmemBytes);
    cudaFuncSetAttribute(gqa_decode_kernel<CfgSmall, 2>, cudaFuncAttributePreferredSharedMemoryCarveout,
                         cudaSharedmemCarveoutMaxShared);
    cudaGetSymbolAddress((void**)&scr, g_scr);
  }
  const __nv_bfloat16* x = (const __nv_bfloat16*)d_in[0];
  const __nv_bfloat16* k = (const __nv_bfloat16*)d_in[1];
  const __nv_bfloat16* v = (const __nv_bfloat16*)d_in[2];
  const __nv_bfloat16* wq = (const __nv_bfloat16*)d_in[3];
  const __nv_bfloat16* wo = (const __nv_bfloat16*)d_in[4];
  if (small)
    gqa_decode_kernel<CfgSmall, 2><<<kG, kThreads, CfgSmall::kSmemBytes, cudaStreamPerThread>>>(
        x, k, v, wq, wo, (__nv_bfloat16*)d_out, scr);
  else
    gqa_decode_kernel<CfgMain, 1><<<kG, kThreads, CfgMain::kSmemBytes, cudaStreamPerThread>>>(
        x, k, v, wq, wo, (__nv_bfloat16*)d_out, scr);
}
```
